```python
import torch

def _softmax(x, axis=-1):
    return torch.softmax(x, dim=axis)
def _gelu(x):
    return torch.nn.functional.gelu(x, approximate="tanh")
def _silu(x):
    return torch.nn.functional.silu(x)
def _sigmoid(x):
    return torch.sigmoid(x)
def _layernorm(x, axis=-1, eps=1e-5):
    m = x.mean(dim=axis, keepdim=True)
    v = x.var(dim=axis, keepdim=True, unbiased=False)
    return (x - m) / torch.sqrt(v + eps)
def _scatter_add(tgt, idx, src, axis=0):
    return tgt.clone().index_add_(axis, idx, src)
def _segment_sum(src, seg, n):
    out = torch.zeros((n,) + src.shape[1:], dtype=src.dtype)
    return out.index_add_(0, seg, src)
def _pad(x, pw):
    flat = tuple(v for pair in reversed(pw) for v in pair)
    return torch.nn.functional.pad(x, flat)

kernel_name = 'recurrent_scan__sliding_block_cached__glu_gated_bilinear__prompt'

def setup_inputs():

    _w = (lambda a: (lambda t: t.to(torch.bfloat16) if t.is_floating_point() else t)(torch.as_tensor(a)))
    def _A_setup():
        B, Sq, D = 1, 2048, 640
        Hq, Hkv, Sk, Dh = 32, 32, 2048, 192
        assert Hq % Hkv == 0, (Hq, Hkv)
        return {
            "x": _w((lambda *s: torch.randn(*s, dtype=torch.bfloat16) * 0.05)(B, Sq, D)),
            "k_cache": _w((lambda *s: torch.randn(*s, dtype=torch.bfloat16) * 1.6)(B, Hkv, Sk, Dh)),
            "v_cache": _w((lambda *s: torch.randn(*s, dtype=torch.bfloat16) * 1.6)(B, Hkv, Sk, Dh)),
            "wq": _w((lambda *s: torch.randn(*s, dtype=torch.bfloat16) * 1.6)(D, Hq * Dh) * (D ** -0.5)),
            "wo": _w((lambda *s: torch.randn(*s, dtype=torch.bfloat16) * 1.6)(Hq * Dh, D) * ((Hq * Dh) ** -0.5)),
        }
    _A_in = _A_setup()

    def _B_setup():
        B, S, D, F = 1, 2048, 640, 1536
        return {
            "x": _w((lambda *s: torch.randn(*s, dtype=torch.bfloat16) * 0.05)(B, S, D)),
            "w_gate": _w((lambda *s: torch.randn(*s, dtype=torch.bfloat16) * 0.2)(D, F) * (D ** -0.5)),
            "w_up": _w((lambda *s: torch.randn(*s, dtype=torch.bfloat16) * 0.2)(D, F) * (D ** -0.5)),
            "w_down": _w((lambda *s: torch.randn(*s, dtype=torch.bfloat16) * 0.2)(F, D) * (F ** -0.5)),
        }
    _B_in = _B_setup()

    return {
        "A_x": _A_in["x"],
        "A_k_cache": _A_in["k_cache"],
        "A_v_cache": _A_in["v_cache"],
        "A_wq": _A_in["wq"],
        "A_wo": _A_in["wo"],
        "B_x": _B_in["x"],
        "B_w_gate": _B_in["w_gate"],
        "B_w_up": _B_in["w_up"],
        "B_w_down": _B_in["w_down"],
    }

def reference(A_x, A_k_cache, A_v_cache, A_wq, A_wo, B_x, B_w_gate, B_w_up, B_w_down):
    def _A_ref(x, k_cache, v_cache, wq, wo):
        B, Sq, D = x.shape
        Hq, Dh = 32, 192
        Hkv, Sk = k_cache.shape[1], k_cache.shape[2]
        W = min(4096, max(256, Sk // 4))
        rep = Hq // Hkv
        q = (lambda x, *d: x.permute(*d))((x @ wq).reshape(B, Sq, Hq, Dh), 0, 2, 1, 3)
        k = (lambda x, n, axis: torch.repeat_interleave(x, n, dim=axis))(k_cache[:, :, Sk - W:, :], rep, axis=1)
        v = (lambda x, n, axis: torch.repeat_interleave(x, n, dim=axis))(v_cache[:, :, Sk - W:, :], rep, axis=1)
        scores = torch.einsum("bhqd,bhkd->bhqk", q, k) * (Dh ** -0.5)
        p = _softmax(scores, axis=-1)
        o = torch.einsum("bhqk,bhkd->bhqd", p, v)
        return (lambda x, *d: x.permute(*d))(o, 0, 2, 1, 3).reshape(B, Sq, Hq * Dh) @ wo

    def _B_ref(x, w_gate, w_up, w_down):
        g = torch.einsum("bsd,df->bsf", x, w_gate)
        u = torch.einsum("bsd,df->bsf", x, w_up)
        h = g * u
        return torch.einsum("bsf,fd->bsd", h, w_down)

    x = A_x
    xn = _layernorm(x, axis=-1)
    s = _A_ref(xn, A_k_cache, A_v_cache, A_wq, A_wo)
    g = _silu(_B_ref(xn, B_w_gate, B_w_up, B_w_down))
    return x + s * g
```

```cpp
#include <cuda_runtime.h>
#include <cuda_bf16.h>
#include <cuda.h>
#include <stdint.h>

namespace {

constexpr int kD = 640, kSK = 2048, kW = 512;
constexpr int kRaw = 4;
constexpr int kGuest = 6;
constexpr int kDecAt = 47;

constexpr int kNA = 5, kNB = 6;
constexpr int kABytes = 16384, kBBytes = 24576, kBFinalBytes = 20480;
constexpr int kOffB = 0;
constexpr int kOffA = kNB * kBBytes;
constexpr int kOffBar = kOffA + kNA * kABytes;
constexpr int kBarFullA = kOffBar;
constexpr int kBarEmptyA = kBarFullA + 8 * kNA;
constexpr int kBarFullB = kBarEmptyA + 8 * kNA;
constexpr int kBarEmptyB = kBarFullB + 8 * kNB;
constexpr int kBarUnit = kBarEmptyB + 8 * kNB;
constexpr int kBarTag = kBarUnit + 8;
constexpr int kBarH = kBarTag + 8;
constexpr int kBarHFree = kBarH + 8;
constexpr int kBarO1 = kBarHFree + 8;
constexpr int kBarO2 = kBarO1 + 8;
constexpr int kBarX = kBarO2 + 8;
constexpr int kBarJob = kBarX + 8;
constexpr int kBarTrig = kBarJob + 8;
constexpr int kBarGuest = kBarTrig + 8;
constexpr int kBarDec = kBarGuest + 8;
constexpr int kBarDone = kBarDec + 8;
constexpr int kOffTag = kBarDone + 8;
constexpr int kOffJob = kOffTag + 4;
constexpr int kOffDec = kOffJob + 4;
constexpr int kOffStat = kOffBar + 384;
constexpr int kSmemBytes = kOffBar + 2048;
constexpr uint32_t kSmemBase = 1024;

constexpr int kXnStride = 4096 + 10 * kABytes;
constexpr int kFlagLN = 32, kFlagUnit = 64  , kFlagD = 72, kFlagGuest = 80  , kFlagX = 128  ;
constexpr int kBalCnt = 0  , kBalList = 64, kBalGuestTag = 96, kBalJob = 128  ;

__device__ __align__(1024) uint8_t g_xn[16 * kXnStride];
__device__ __align__(1024) uint8_t g_acat[16 * 96 * kABytes];
__device__ __align__(1024) uint32_t g_bal[128 + 32 * 32];
__device__ __align__(1024) uint4 g_xs[128 * 12 * 128];
__device__ __align__(1024) uint4 g_xg[128 * 5 * 256];
__device__ __align__(1024) uint4 g_xd[128 * 5 * 256];

__device__ __forceinline__ uint32_t smem_u32(const void* p) { return (uint32_t)__cvta_generic_to_shared(p); }
__device__ __forceinline__ void mbar_init(uint32_t bar, int cnt) {
  asm volatile("mbarrier.init.shared::cta.b64 [%0], %1;" ::"r"(bar), "r"(cnt) : "memory");
}
__device__ __forceinline__ void mbar_expect_tx(uint32_t bar, int bytes) {
  asm volatile("mbarrier.arrive.expect_tx.shared::cta.b64 _, [%0], %1;" ::"r"(bar), "r"(bytes) : "memory");
}
__device__ __forceinline__ void mbar_expect_tx_cta(uint32_t bar, int bytes, uint32_t cta) {
  asm volatile("{\n.reg .b32 ra;\nmapa.shared::cluster.u32 ra, %0, %2;\n"
               "mbarrier.arrive.expect_tx.shared::cluster.b64 _, [ra], %1;\n}\n" ::"r"(bar), "r"(bytes), "r"(cta) : "memory");
}
__device__ __forceinline__ void mbar_arrive(uint32_t bar) {
  asm volatile("mbarrier.arrive.shared::cta.b64 _, [%0];" ::"r"(bar) : "memory");
}
__device__ __forceinline__ void mbar_arrive_if0(uint32_t bar, uint32_t skip) {
  asm volatile("{\n.reg .pred p;\nsetp.eq.u32 p, %1, 0;\n@p mbarrier.arrive.shared::cta.b64 _, [%0];\n}\n" ::"r"(bar), "r"(skip) : "memory");
}
__device__ __forceinline__ void mbar_arrive_cta_if0(uint32_t bar, uint32_t cta, uint32_t skip) {
  asm volatile("{\n.reg .pred p;\n.reg .b32 ra;\nsetp.eq.u32 p, %2, 0;\nmapa.shared::cluster.u32 ra, %0, %1;\n"
               "@p mbarrier.arrive.shared::cluster.b64 _, [ra];\n}\n" ::"r"(bar), "r"(cta), "r"(skip) : "memory");
}
__device__ __forceinline__ void mbar_wait(uint32_t bar, uint32_t parity) {
  asm volatile("{\n.reg .pred p;\n.reg .u32 c;\nmov.u32 c, 0;\n"
               "LAB_WAIT:\nmbarrier.try_wait.parity.shared::cta.b64 p, [%0], %1;\n@p bra DONE;\n"
               "add.u32 c, c, 1;\nsetp.lt.u32 p, c, 0x200000;\n@p bra LAB_WAIT;\ntrap;\nDONE:\n}\n" ::"r"(bar), "r"(parity) : "memory");
}
__device__ __forceinline__ void mbar_wait_sleep(uint32_t bar, uint32_t parity) {
  asm volatile("{\n.reg .pred p;\n.reg .u32 c;\nmov.u32 c, 0;\n"
               "LAB_WAIT:\nmbarrier.try_wait.parity.shared::cta.b64 p, [%0], %1, 20000;\n@p bra DONE;\n"
               "add.u32 c, c, 1;\nsetp.lt.u32 p, c, 0x40000;\n@p bra LAB_WAIT;\ntrap;\nDONE:\n}\n" ::"r"(bar), "r"(parity) : "memory");
}
__device__ __forceinline__ uint32_t mbar_probe(uint32_t bar, uint32_t parity) {
  uint32_t ok;
  asm volatile("{\n.reg .pred p;\nmbarrier.test_wait.parity.shared::cta.b64 p, [%1], %2;\nselp.u32 %0, 1, 0, p;\n}\n"
               : "=r"(ok) : "r"(bar), "r"(parity) : "memory");
  return ok;
}
__device__ __forceinline__ void mbar_wait_unless(uint32_t ok, uint32_t bar, uint32_t parity) {
  asm volatile("{\n.reg .pred p;\nsetp.ne.u32 p, %2, 0;\n"
               "LAB_WAIT:\n@!p mbarrier.try_wait.parity.shared::cta.b64 p, [%0], %1;\n@!p bra LAB_WAIT;\n}\n" ::"r"(bar), "r"(parity), "r"(ok) : "memory");
}
__device__ __forceinline__ uint32_t mbar_probe2(uint32_t bar0, uint32_t par0, uint32_t bar1, uint32_t par1) {
  uint32_t ok;
  asm volatile("{\n.reg .pred p, q;\nmbarrier.test_wait.parity.shared::cta.b64 p, [%1], %2;\n"
               "mbarrier.test_wait.parity.shared::cta.b64 q, [%3], %4;\nand.pred p, p, q;\nselp.u32 %0, 1, 0, p;\n}\n"
               : "=r"(ok) : "r"(bar0), "r"(par0), "r"(bar1), "r"(par1) : "memory");
  return ok;
}
__device__ __forceinline__ void mbar_wait2_unless(uint32_t ok, uint32_t bar0, uint32_t par0, uint32_t bar1, uint32_t par1) {
  asm volatile("{\n.reg .pred p, q;\nsetp.ne.u32 p, %4, 0;\n@p bra DONE;\n"
               "LAB_WAIT:\nmbarrier.try_wait.parity.shared::cta.b64 q, [%0], %1;\n"
               "mbarrier.try_wait.parity.shared::cta.b64 p, [%2], %3;\nand.pred p, p, q;\n@!p bra LAB_WAIT;\nDONE:\n}\n"
               ::"r"(bar0), "r"(par0), "r"(bar1), "r"(par1), "r"(ok) : "memory");
}
__device__ __forceinline__ void poll_ge(const uint32_t* p, uint32_t target) {
  asm volatile("{\n.reg .pred p;\n.reg .u32 c, v;\n.reg .s32 d;\nmov.u32 c, 0;\n"
               "LAB_POLL:\nld.acquire.gpu.global.u32 v, [%0];\nsub.s32 d, v, %1;\nsetp.ge.s32 p, d, 0;\n@p bra DONE;\n"
               "add.u32 c, c, 1;\nsetp.lt.u32 p, c, 0x1000000;\n@p bra LAB_POLL;\ntrap;\nDONE:\n}\n" ::"l"(p), "r"(target) : "memory");
}
__device__ __forceinline__ void poll_ge_relaxed(const uint32_t* p, uint32_t target) {
  asm volatile("{\n.reg .pred p;\n.reg .u32 c, v;\n.reg .s32 d;\nmov.u32 c, 0;\n"
               "LAB_POLL:\nld.relaxed.gpu.global.u32 v, [%0];\nsub.s32 d, v, %1;\nsetp.ge.s32 p, d, 0;\n@p bra DONE;\n"
               "add.u32 c, c, 1;\nsetp.lt.u32 p, c, 0x1000000;\n@p bra LAB_POLL;\ntrap;\nDONE:\n}\n" ::"l"(p), "r"(target) : "memory");
}
__device__ __forceinline__ void poll_ge_sleep(const uint32_t* p, uint32_t target) {
  asm volatile("{\n.reg .pred p;\n.reg .u32 c, v;\n.reg .s32 d;\nmov.u32 c, 0;\n"
               "LAB_POLL:\nld.acquire.gpu.global.u32 v, [%0];\nsub.s32 d, v, %1;\nsetp.ge.s32 p, d, 0;\n@p bra DONE;\n"
               "nanosleep.u32 700;\nadd.u32 c, c, 1;\nsetp.lt.u32 p, c, 0x400000;\n@p bra LAB_POLL;\ntrap;\nDONE:\n}\n" ::"l"(p), "r"(target) : "memory");
}
__device__ __forceinline__ uint32_t map_cta(uint32_t addr, uint32_t cta) {
  uint32_t r;
  asm("mapa.shared::cluster.u32 %0, %1, %2;" : "=r"(r) : "r"(addr), "r"(cta));
  return r;
}
__device__ __forceinline__ void broadcast_word(uint32_t addr, uint32_t v, uint32_t bar) {
#pragma unroll
  for (uint32_t c = 0; c < 2; c++)
    asm volatile("st.async.weak.shared::cluster.mbarrier::complete_tx::bytes.u32 [%0], %1, [%2];" ::"r"(map_cta(addr, c)), "r"(v), "r"(map_cta(bar, c)) : "memory");
}
__device__ __forceinline__ uint32_t lds32(uint32_t addr) {
  uint32_t v;
  asm volatile("ld.shared.u32 %0, [%1];" : "=r"(v) : "r"(addr) : "memory");
  return v;
}
__device__ __forceinline__ uint32_t ld_relaxed(const uint32_t* p) {
  uint32_t v;
  asm volatile("ld.relaxed.gpu.global.u32 %0, [%1];" : "=r"(v) : "l"(p) : "memory");
  return v;
}
__device__ __forceinline__ void st_relaxed(uint32_t* p, uint32_t v) {
  asm volatile("st.relaxed.gpu.global.u32 [%0], %1;" ::"l"(p), "r"(v) : "memory");
}
__device__ __forceinline__ void stg32(uint64_t addr, uint32_t v) {
  asm volatile("st.global.u32 [%0], %1;" ::"l"(addr), "r"(v) : "memory");
}
__device__ __forceinline__ void red_release_add(uint32_t* p) {
  asm volatile("red.release.gpu.global.add.u32 [%0], 1;" ::"l"(p) : "memory");
}
__device__ __forceinline__ uint64_t policy_evict_first() {
  uint64_t p;
  asm volatile("createpolicy.fractional.L2::evict_first.b64 %0, 1.0;" : "=l"(p));
  return p;
}
__device__ __forceinline__ void bulk_load(uint32_t dst, const void* src, int bytes, uint32_t bar) {
  asm volatile("cp.async.bulk.shared::cluster.global.mbarrier::complete_tx::bytes [%0], [%1], %2, [%3];" ::"r"(dst), "l"(src), "r"(bytes), "r"(bar) : "memory");
}
__device__ __forceinline__ void bulk_load_hint(uint32_t dst, const void* src, int bytes, uint32_t bar, uint64_t pol) {
  asm volatile("cp.async.bulk.shared::cluster.global.mbarrier::complete_tx::bytes.L2::cache_hint [%0], [%1], %2, [%3], %4;" ::"r"(dst), "l"(src), "r"(bytes), "r"(bar), "l"(pol) : "memory");
}
__device__ __forceinline__ void tma3_mc(uint32_t dst, const CUtensorMap* tm, int c1, int c2, uint32_t bar, uint64_t pol) {
  asm volatile("cp.async.bulk.tensor.3d.shared::cluster.global.mbarrier::complete_tx::bytes.multicast::cluster.L2::cache_hint [%0], [%1, {%3, %4, %5}], [%2], %6, %7;"
               ::"r"(dst), "l"(tm), "r"(bar), "r"(0), "r"(c1), "r"(c2), "h"((uint16_t)3), "l"(pol) : "memory");
}
__device__ __forceinline__ void tma3(uint32_t dst, const CUtensorMap* tm, int c1, int c2, uint32_t bar) {
  asm volatile("cp.async.bulk.tensor.3d.shared::cluster.global.mbarrier::complete_tx::bytes [%0], [%1, {%3, %4, %5}], [%2];"
               ::"r"(dst), "l"(tm), "r"(bar), "r"(0), "r"(c1), "r"(c2) : "memory");
}
__host__ __device__ constexpr uint32_t desc_lo(uint32_t addr, uint32_t lbo) { return (addr >> 4) | ((lbo >> 4) << 16); }
__host__ __device__ constexpr uint32_t desc_hi(uint32_t sbo, uint32_t swz) { return (sbo >> 4) | (swz << 30); }
__device__ __forceinline__ uint64_t mk(uint32_t lo, uint32_t hi) { return ((uint64_t)hi << 32) | lo; }
__device__ __forceinline__ uint32_t pack_bf16(float lo, float hi) {
  uint32_t r;
  asm("cvt.rn.bf16x2.f32 %0, %1, %2;" : "=r"(r) : "f"(hi), "f"(lo));
  return r;
}
__device__ __forceinline__ float bf_lo(uint32_t v) { return __uint_as_float(v << 16); }
__device__ __forceinline__ float bf_hi(uint32_t v) { return __uint_as_float(v & 0xffff0000u); }
__device__ __forceinline__ float ex2(float x) {
  float y;
  asm("ex2.approx.ftz.f32 %0, %1;" : "=f"(y) : "f"(x));
  return y;
}
__device__ __forceinline__ float rcp(float x) {
  float y;
  asm("rcp.approx.ftz.f32 %0, %1;" : "=f"(y) : "f"(x));
  return y;
}
__device__ __forceinline__ uint32_t hsub2(uint32_t a, uint32_t b) { uint32_t r; asm("sub.rn.bf16x2 %0, %1, %2;" : "=r"(r) : "r"(a), "r"(b)); return r; }
__device__ __forceinline__ uint32_t hadd2(uint32_t a, uint32_t b) { uint32_t r; asm("add.rn.bf16x2 %0, %1, %2;" : "=r"(r) : "r"(a), "r"(b)); return r; }
__device__ __forceinline__ uint32_t hmul2(uint32_t a, uint32_t b) { uint32_t r; asm("mul.rn.bf16x2 %0, %1, %2;" : "=r"(r) : "r"(a), "r"(b)); return r; }
__device__ __forceinline__ uint32_t hfma2(uint32_t a, uint32_t b, uint32_t c) { uint32_t r; asm("fma.rn.bf16x2 %0, %1, %2, %3;" : "=r"(r) : "r"(a), "r"(b), "r"(c)); return r; }
__device__ __forceinline__ float silu(float d) { return d * rcp(1.f + ex2(d * -1.4426950408889634f)); }
template <int n> __device__ __forceinline__ void fence_regs(float (&d)[n]) {
#pragma unroll
  for (int i = 0; i < n; i++) asm volatile("" : "+f"(d[i])::"memory");
}
template <int n> __device__ __forceinline__ void fence_regs(uint32_t (&d)[n]) {
#pragma unroll
  for (int i = 0; i < n; i++) asm volatile("" : "+r"(d[i])::"memory");
}
#define WG_FENCE() asm volatile("wgmma.fence.sync.aligned;" ::: "memory")
#define WG_COMMIT() asm volatile("wgmma.commit_group.sync.aligned;" ::: "memory")
#define WG_WAIT(n) asm volatile("wgmma.wait_group.sync.aligned %0;" ::"n"(n) : "memory")

template <int TB, int S> __device__ __forceinline__ void wgmma_ss_n192(float (&d)[S], uint64_t da, uint64_t db, int sd) {
  asm volatile("{\n.reg .pred p;\nsetp.ne.b32 p, %98, 0;\n"
    "wgmma.mma_async.sync.aligned.m64n192k16.f32.bf16.bf16 "
    "{%0, %1, %2, %3, %4, %5, %6, %7, %8, %9, %10, %11, %12, %13, %14, %15, %16, %17, %18, %19, %20, %21, %22, %23, %24, %25, %26, %27, %28, %29, %30, %31, %32, %33, %34, %35, %36, %37, %38, %39, %40, %41, %42, %43, %44, %45, %46, %47, %48, %49, %50, %51, %52, %53, %54, %55, %56, %57, %58, %59, %60, %61, %62, %63, %64, %65, %66, %67, %68, %69, %70, %71, %72, %73, %74, %75, %76, %77, %78, %79, %80, %81, %82, %83, %84, %85, %86, %87, %88, %89, %90, %91, %92, %93, %94, %95}, "
    "%96, %97, p, 1, 1, 0, %99;\n}\n"
    : "+f"(d[0]), "+f"(d[1]), "+f"(d[2]), "+f"(d[3]), "+f"(d[4]), "+f"(d[5]), "+f"(d[6]), "+f"(d[7]), "+f"(d[8]), "+f"(d[9]), "+f"(d[10]), "+f"(d[11]), "+f"(d[12]), "+f"(d[13]), "+f"(d[14]), "+f"(d[15]), "+f"(d[16]), "+f"(d[17]), "+f"(d[18]), "+f"(d[19]), "+f"(d[20]), "+f"(d[21]), "+f"(d[22]), "+f"(d[23]), "+f"(d[24]), "+f"(d[25]), "+f"(d[26]), "+f"(d[27]), "+f"(d[28]), "+f"(d[29]), "+f"(d[30]), "+f"(d[31]), "+f"(d[32]), "+f"(d[33]), "+f"(d[34]), "+f"(d[35]), "+f"(d[36]), "+f"(d[37]), "+f"(d[38]), "+f"(d[39]), "+f"(d[40]), "+f"(d[41]), "+f"(d[42]), "+f"(d[43]), "+f"(d[44]), "+f"(d[45]), "+f"(d[46]), "+f"(d[47]), "+f"(d[48]), "+f"(d[49]), "+f"(d[50]), "+f"(d[51]), "+f"(d[52]), "+f"(d[53]), "+f"(d[54]), "+f"(d[55]), "+f"(d[56]), "+f"(d[57]), "+f"(d[58]), "+f"(d[59]), "+f"(d[60]), "+f"(d[61]), "+f"(d[62]), "+f"(d[63]), "+f"(d[64]), "+f"(d[65]), "+f"(d[66]), "+f"(d[67]), "+f"(d[68]), "+f"(d[69]), "+f"(d[70]), "+f"(d[71]), "+f"(d[72]), "+f"(d[73]), "+f"(d[74]), "+f"(d[75]), "+f"(d[76]), "+f"(d[77]), "+f"(d[78]), "+f"(d[79]), "+f"(d[80]), "+f"(d[81]), "+f"(d[82]), "+f"(d[83]), "+f"(d[84]), "+f"(d[85]), "+f"(d[86]), "+f"(d[87]), "+f"(d[88]), "+f"(d[89]), "+f"(d[90]), "+f"(d[91]), "+f"(d[92]), "+f"(d[93]), "+f"(d[94]), "+f"(d[95])
    : "l"(da), "l"(db), "r"(sd), "n"(TB));
}
template <int TB, int S> __device__ __forceinline__ void wgmma_ss_n160(float (&d)[S], uint64_t da, uint64_t db, int sd) {
  asm volatile("{\n.reg .pred p;\nsetp.ne.b32 p, %82, 0;\n"
    "wgmma.mma_async.sync.aligned.m64n160k16.f32.bf16.bf16 "
    "{%0, %1, %2, %3, %4, %5, %6, %7, %8, %9, %10, %11, %12, %13, %14, %15, %16, %17, %18, %19, %20, %21, %22, %23, %24, %25, %26, %27, %28, %29, %30, %31, %32, %33, %34, %35, %36, %37, %38, %39, %40, %41, %42, %43, %44, %45, %46, %47, %48, %49, %50, %51, %52, %53, %54, %55, %56, %57, %58, %59, %60, %61, %62, %63, %64, %65, %66, %67, %68, %69, %70, %71, %72, %73, %74, %75, %76, %77, %78, %79}, "
    "%80, %81, p, 1, 1, 0, %83;\n}\n"
    : "+f"(d[0]), "+f"(d[1]), "+f"(d[2]), "+f"(d[3]), "+f"(d[4]), "+f"(d[5]), "+f"(d[6]), "+f"(d[7]), "+f"(d[8]), "+f"(d[9]), "+f"(d[10]), "+f"(d[11]), "+f"(d[12]), "+f"(d[13]), "+f"(d[14]), "+f"(d[15]), "+f"(d[16]), "+f"(d[17]), "+f"(d[18]), "+f"(d[19]), "+f"(d[20]), "+f"(d[21]), "+f"(d[22]), "+f"(d[23]), "+f"(d[24]), "+f"(d[25]), "+f"(d[26]), "+f"(d[27]), "+f"(d[28]), "+f"(d[29]), "+f"(d[30]), "+f"(d[31]), "+f"(d[32]), "+f"(d[33]), "+f"(d[34]), "+f"(d[35]), "+f"(d[36]), "+f"(d[37]), "+f"(d[38]), "+f"(d[39]), "+f"(d[40]), "+f"(d[41]), "+f"(d[42]), "+f"(d[43]), "+f"(d[44]), "+f"(d[45]), "+f"(d[46]), "+f"(d[47]), "+f"(d[48]), "+f"(d[49]), "+f"(d[50]), "+f"(d[51]), "+f"(d[52]), "+f"(d[53]), "+f"(d[54]), "+f"(d[55]), "+f"(d[56]), "+f"(d[57]), "+f"(d[58]), "+f"(d[59]), "+f"(d[60]), "+f"(d[61]), "+f"(d[62]), "+f"(d[63]), "+f"(d[64]), "+f"(d[65]), "+f"(d[66]), "+f"(d[67]), "+f"(d[68]), "+f"(d[69]), "+f"(d[70]), "+f"(d[71]), "+f"(d[72]), "+f"(d[73]), "+f"(d[74]), "+f"(d[75]), "+f"(d[76]), "+f"(d[77]), "+f"(d[78]), "+f"(d[79])
    : "l"(da), "l"(db), "r"(sd), "n"(TB));
}
template <int TB, int S> __device__ __forceinline__ void wgmma_rs_n64(float (&d)[S], uint32_t a0, uint32_t a1, uint32_t a2, uint32_t a3, uint64_t db, int sd) {
  asm volatile("{\n.reg .pred p;\nsetp.ne.b32 p, %37, 0;\n"
    "wgmma.mma_async.sync.aligned.m64n64k16.f32.bf16.bf16 "
    "{%0, %1, %2, %3, %4, %5, %6, %7, %8, %9, %10, %11, %12, %13, %14, %15, %16, %17, %18, %19, %20, %21, %22, %23, %24, %25, %26, %27, %28, %29, %30, %31}, "
    "{%32, %33, %34, %35}, %36, p, 1, 1, %38;\n}\n"
    : "+f"(d[0]), "+f"(d[1]), "+f"(d[2]), "+f"(d[3]), "+f"(d[4]), "+f"(d[5]), "+f"(d[6]), "+f"(d[7]), "+f"(d[8]), "+f"(d[9]), "+f"(d[10]), "+f"(d[11]), "+f"(d[12]), "+f"(d[13]), "+f"(d[14]), "+f"(d[15]), "+f"(d[16]), "+f"(d[17]), "+f"(d[18]), "+f"(d[19]), "+f"(d[20]), "+f"(d[21]), "+f"(d[22]), "+f"(d[23]), "+f"(d[24]), "+f"(d[25]), "+f"(d[26]), "+f"(d[27]), "+f"(d[28]), "+f"(d[29]), "+f"(d[30]), "+f"(d[31])
    : "r"(a0), "r"(a1), "r"(a2), "r"(a3), "l"(db), "r"(sd), "n"(TB));
}
template <int TB, int S> __device__ __forceinline__ void wgmma_rs_n192(float (&d)[S], uint32_t a0, uint32_t a1, uint32_t a2, uint32_t a3, uint64_t db, int sd) {
  asm volatile("{\n.reg .pred p;\nsetp.ne.b32 p, %101, 0;\n"
    "wgmma.mma_async.sync.aligned.m64n192k16.f32.bf16.bf16 "
    "{%0, %1, %2, %3, %4, %5, %6, %7, %8, %9, %10, %11, %12, %13, %14, %15, %16, %17, %18, %19, %20, %21, %22, %23, %24, %25, %26, %27, %28, %29, %30, %31, %32, %33, %34, %35, %36, %37, %38, %39, %40, %41, %42, %43, %44, %45, %46, %47, %48, %49, %50, %51, %52, %53, %54, %55, %56, %57, %58, %59, %60, %61, %62, %63, %64, %65, %66, %67, %68, %69, %70, %71, %72, %73, %74, %75, %76, %77, %78, %79, %80, %81, %82, %83, %84, %85, %86, %87, %88, %89, %90, %91, %92, %93, %94, %95}, "
    "{%96, %97, %98, %99}, %100, p, 1, 1, %102;\n}\n"
    : "+f"(d[0]), "+f"(d[1]), "+f"(d[2]), "+f"(d[3]), "+f"(d[4]), "+f"(d[5]), "+f"(d[6]), "+f"(d[7]), "+f"(d[8]), "+f"(d[9]), "+f"(d[10]), "+f"(d[11]), "+f"(d[12]), "+f"(d[13]), "+f"(d[14]), "+f"(d[15]), "+f"(d[16]), "+f"(d[17]), "+f"(d[18]), "+f"(d[19]), "+f"(d[20]), "+f"(d[21]), "+f"(d[22]), "+f"(d[23]), "+f"(d[24]), "+f"(d[25]), "+f"(d[26]), "+f"(d[27]), "+f"(d[28]), "+f"(d[29]), "+f"(d[30]), "+f"(d[31]), "+f"(d[32]), "+f"(d[33]), "+f"(d[34]), "+f"(d[35]), "+f"(d[36]), "+f"(d[37]), "+f"(d[38]), "+f"(d[39]), "+f"(d[40]), "+f"(d[41]), "+f"(d[42]), "+f"(d[43]), "+f"(d[44]), "+f"(d[45]), "+f"(d[46]), "+f"(d[47]), "+f"(d[48]), "+f"(d[49]), "+f"(d[50]), "+f"(d[51]), "+f"(d[52]), "+f"(d[53]), "+f"(d[54]), "+f"(d[55]), "+f"(d[56]), "+f"(d[57]), "+f"(d[58]), "+f"(d[59]), "+f"(d[60]), "+f"(d[61]), "+f"(d[62]), "+f"(d[63]), "+f"(d[64]), "+f"(d[65]), "+f"(d[66]), "+f"(d[67]), "+f"(d[68]), "+f"(d[69]), "+f"(d[70]), "+f"(d[71]), "+f"(d[72]), "+f"(d[73]), "+f"(d[74]), "+f"(d[75]), "+f"(d[76]), "+f"(d[77]), "+f"(d[78]), "+f"(d[79]), "+f"(d[80]), "+f"(d[81]), "+f"(d[82]), "+f"(d[83]), "+f"(d[84]), "+f"(d[85]), "+f"(d[86]), "+f"(d[87]), "+f"(d[88]), "+f"(d[89]), "+f"(d[90]), "+f"(d[91]), "+f"(d[92]), "+f"(d[93]), "+f"(d[94]), "+f"(d[95])
    : "r"(a0), "r"(a1), "r"(a2), "r"(a3), "l"(db), "r"(sd), "n"(TB));
}

struct Ring {
  uint32_t idx, phase;
  template <int N> __device__ __forceinline__ void next() {
    if (++idx == N) { idx = 0; phase ^= 1; }
  }
};

__global__ void __cluster_dims__(2, 1, 1) __launch_bounds__(384, 1)
fused_kernel(const __nv_bfloat16* __restrict__ x, __nv_bfloat16* __restrict__ out, uint8_t* const xnb,
             const __grid_constant__ CUtensorMap tmX, const __grid_constant__ CUtensorMap tmWg,
             const __grid_constant__ CUtensorMap tmWu, const __grid_constant__ CUtensorMap tmWq,
             const __grid_constant__ CUtensorMap tmK, const __grid_constant__ CUtensorMap tmV,
             const __grid_constant__ CUtensorMap tmWo, const __grid_constant__ CUtensorMap tmWd) {
  uint32_t xin[20];
  {
    const uint32_t row = (blockIdx.x & 15) * 128 + (blockIdx.x & ~15u) + (threadIdx.x >> 4);
    const uint8_t* xr = reinterpret_cast<const uint8_t*>(x) + (row * (kD * 2) + (threadIdx.x & 15) * 16);
    asm volatile("{\n.reg .pred p;\nsetp.ge.u32 p, %21, 256;\n@p bra.uni LAB_SKIP;\n"
                 "ld.global.nc.v4.u32 {%0, %1, %2, %3}, [%20];\nld.global.nc.v4.u32 {%4, %5, %6, %7}, [%20+256];\n"
                 "ld.global.nc.v4.u32 {%8, %9, %10, %11}, [%20+512];\nld.global.nc.v4.u32 {%12, %13, %14, %15}, [%20+768];\n"
                 "ld.global.nc.v4.u32 {%16, %17, %18, %19}, [%20+1024];\nLAB_SKIP:\n}\n"
                 : "=&r"(xin[0]), "=&r"(xin[1]), "=&r"(xin[2]), "=&r"(xin[3]), "=&r"(xin[4]), "=&r"(xin[5]), "=&r"(xin[6]), "=&r"(xin[7]),
                   "=&r"(xin[8]), "=&r"(xin[9]), "=&r"(xin[10]), "=&r"(xin[11]), "=&r"(xin[12]), "=&r"(xin[13]), "=&r"(xin[14]), "=&r"(xin[15]),
                   "=&r"(xin[16]), "=&r"(xin[17]), "=&r"(xin[18]), "=&r"(xin[19])
                 : "l"(xr), "r"(threadIdx.x + (blockIdx.x & 128) * 2) : "memory");
  }
  extern __shared__ __align__(1024) uint8_t smem_raw[];
  const uint32_t sbase = smem_u32(smem_raw);
  const int tid = threadIdx.x;
  const int warp = __shfl_sync(0xffffffffu, tid >> 5, 0);
  const int wg = warp >> 2;
  const int lane = tid & 31;
  const uint32_t rank = blockIdx.x & 1;
  const int cl = blockIdx.x >> 1;
  const int ti = (cl & 7) * 2 + rank;
  const int j = cl >> 3;
  const int nq = j & 3, kh = j >> 2;
  uint32_t* flags = reinterpret_cast<uint32_t*>(xnb + (uint32_t)(ti * kXnStride));
  const bool guest = cl >= 64;
  const uint32_t gh = gridDim.x > 128 ? kGuest / 2 : 0;

  uint8_t* const stat = reinterpret_cast<uint8_t*>(flags) + 2048;
  uint32_t tag;
  asm volatile("{\n.reg .pred p;\nsetp.lt.u32 p, %2, 64;\n@p ld.relaxed.gpu.global.u32 %0, [%1];\n}\n"
               : "=r"(tag) : "l"(stat + (16 * j + (tid & 15)) * 8), "r"(cl + (tid >> 8) * 64) : "memory");
  if (wg == 2) {
    if (tid == 256) {
      mbar_init(sbase + kBarFullA, 1);
      mbar_init(sbase + kBarFullB, 1);
      mbar_init(sbase + kBarFullB + 8, 1);
      asm volatile("fence.proxy.async.shared::cta;" ::: "memory");
      if (!guest) {
        mbar_expect_tx(sbase + kBarFullA, kRaw * kABytes);
        tma3(sbase + kOffA, &tmX, ti * 128, 0, sbase + kBarFullA);
        mbar_expect_tx(sbase + kBarFullB, kBBytes);
        tma3(sbase + kOffB, &tmWg, 0, 3 * j, sbase + kBarFullB);
        mbar_expect_tx(sbase + kBarFullB + 8, kBBytes);
        tma3(sbase + kOffB + kBBytes, &tmWu, 0, 3 * j, sbase + kBarFullB + 8);
      }
    } else if (tid == 288) {
#pragma unroll
      for (int s = 1; s < kNA; s++) mbar_init(sbase + kBarFullA + 8 * s, 1);
#pragma unroll
      for (int s = 2; s < kNB; s++) mbar_init(sbase + kBarFullB + 8 * s, 1);
#pragma unroll
      for (int s = kBarTag; s < kBarDec; s += 8) mbar_init(sbase + s, 1);
#pragma unroll
      for (int s = 1; s < kRaw; s++) if (!guest) mbar_arrive(sbase + kBarFullA + 8 * s);
      mbar_expect_tx(sbase + kBarJob, 4);
    } else if (tid == 320) {
#pragma unroll
      for (int s = 0; s < kNA; s++) mbar_init(sbase + kBarEmptyA + 8 * s, 2);
#pragma unroll
      for (int s = 0; s < kNB; s++) mbar_init(sbase + kBarEmptyB + 8 * s, 4);
      mbar_init(sbase + kBarUnit, 8);
      mbar_init(sbase + kBarDone, 2);
      mbar_init(sbase + kBarDec, 2);
      mbar_expect_tx(sbase + kBarDec, 4);
    }
    asm volatile("fence.mbarrier_init.release.cluster;" ::: "memory");
  }
  __syncwarp();
  asm volatile("barrier.cluster.arrive.relaxed.aligned;" ::: "memory");

  if (wg == 2) {
    asm volatile("setmaxnreg.dec.sync.aligned.u32 24;");
    if ((sbase & 0xFFFFFFu) != kSmemBase) asm volatile("trap;");
    asm volatile("barrier.cluster.wait.aligned;" ::: "memory");
#define TAG lds32(sbase + kOffTag)
    auto get_job = [&]() -> uint32_t {
      if (!kh) return cl & 31;
      mbar_wait_sleep(sbase + kBarJob, 0);
      return lds32(sbase + kOffJob);
    };
    auto final_chunk = [&](uint32_t n) -> uint32_t {
      return kh ? (n < 48 ? n + 24 : (n < 54 ? 131 : 149) - n) : n + (n < 48 ? gh : (n < 54 ? 24 : 30));
    };
    if (warp == 8 && lane == 0) {
      const uint64_t pol = policy_evict_first();
      uint32_t slot = (guest ? 0 : 2) + rank, phase = 1;
      auto issue = [&](const CUtensorMap* tm, int c1, int c2, int bytes) {
        mbar_wait_sleep(sbase + kBarEmptyB + 8 * slot, phase);
        const uint32_t fb = sbase + kBarFullB + 8 * slot;
        mbar_expect_tx(fb, bytes);
        mbar_expect_tx_cta(fb, bytes, rank ^ 1);
        tma3_mc(sbase + kOffB + slot * kBBytes, tm, c1, c2, fb, pol);
        slot += 2;
        if (slot >= kNB) { slot -= kNB; phase ^= 1; }
      };
      if (!guest) mbar_wait_sleep(sbase + kBarFullB + 8 * rank, 0);
      uint32_t nend = 0;
#pragma unroll 1
      for (int run = 0; run < (guest ? 16 : 24); run++) {
        const CUtensorMap* tm = &tmWo;
        int c1 = rank * 64, step = 128, cnt, c2, bytes = kBFinalBytes;
        if (guest) {
          cnt = kGuest / 2; c2 = 5 * ((cl & 1) * 2 + (run >> 3));
        } else if (run == 0) {
          tm = rank ? &tmWu : &tmWg; c1 = 64; step = 64; cnt = 9; c2 = 3 * j; bytes = kBBytes;
        } else if (run < 21) {
          const int t = ((run - 1) * 52) >> 8, part = run - 1 - 5 * t, h = 8 * t + j;
          const int row = h * kSK + (kSK - kW);
          bytes = kBBytes; c2 = 3 * h; tm = &tmWq; cnt = 4;
          if (part == 1) { tm = &tmWd; cnt = kh && t == 1 ? 12 : 0; c2 = 5 * nq; bytes = kBFinalBytes; }
          if (part == 2) { c1 += 512; cnt = 1; }
          if (part == 3) { tm = &tmK; c1 += row; step = 64; cnt = rank ? 7 : 1; c2 = 0; }
          if (part == 4) { tm = &tmV; c1 = row + rank * 448; step = 64; cnt = rank ? 1 : 7; c2 = 0; }
        } else {
          c2 = 5 * (get_job() >> 3);
          const uint32_t par = (gh + rank) & 1;
          uint32_t n0 = (run == 21 ? 24 * kh + gh + rank : (run == 22 ? 48 : 54) + par);
          nend = run == 21 ? 48 : 54;
          if (run == 23) {
            mbar_wait_sleep(sbase + kBarDec, 0);
            nend += lds32(sbase + kOffDec);
          }
          cnt = n0 < nend ? (nend - n0 + 1) >> 1 : 0;
          c1 = final_chunk(n0) * 64;
          if (kh && run > 21) step = -128;
        }
#pragma unroll 1
        for (; cnt > 0; cnt--, c1 += step) issue(tm, c1, c2, bytes);
      }
      if (!guest) mbar_wait_sleep(sbase + kBarDone, 0);
    } else if (warp == 9 && lane == 0) {
      const uint64_t pol = policy_evict_first();
      if (guest) {
        uint32_t* tp = g_bal + kBalGuestTag + (blockIdx.x & 3);
        const uint32_t tag = ld_relaxed(tp) + 1;
        st_relaxed(tp, tag);
#pragma unroll 1
        for (uint32_t off = rank * kXnStride; off < 16 * kXnStride; off += 2 * kXnStride)
          poll_ge_sleep(reinterpret_cast<const uint32_t*>(xnb + off) + kFlagUnit + 1, tag * 8);
        asm volatile("fence.proxy.async.global;" ::: "memory");
        Ring rg{0, 1};
#pragma unroll 1
        for (int i = 0; i < 16; i++)
#pragma unroll 1
          for (uint32_t c = 0; c < kGuest; c++) {
            mbar_wait_sleep(sbase + kBarEmptyA + 8 * rg.idx, rg.phase);
            const uint32_t fb = sbase + kBarFullA + 8 * rg.idx;
            mbar_expect_tx(fb, kABytes);
            bulk_load(sbase + kOffA + rg.idx * kABytes, g_acat + ((((i & 7) * 2 + rank) * 96 + c) << 14), kABytes, fb);
            rg.next<kNA>();
          }
        return;
      }
      mbar_wait_sleep(sbase + kBarTag, 0);
      const uint8_t* xn = reinterpret_cast<const uint8_t*>(flags) + 4096;
      poll_ge(flags + kFlagLN, TAG * 8);
      asm volatile("fence.proxy.async.global;" ::: "memory");
      Ring ra{kRaw, 1};
      auto load_acat = [&](uint32_t chunk) {
        mbar_wait_sleep(sbase + kBarEmptyA + 8 * ra.idx, ra.phase);
        const uint32_t fb = sbase + kBarFullA + 8 * ra.idx;
        mbar_expect_tx(fb, kABytes);
        bulk_load_hint(sbase + kOffA + ra.idx * kABytes, g_acat + (chunk << 14), kABytes, fb, pol);
        ra.next<kNA>();
      };
#pragma unroll 1
      for (int pass = 0; pass < 5; pass++) {
        if (pass == 4 - kh) mbar_wait_sleep(sbase + kBarHFree, 0);
#pragma unroll 1
        for (uint32_t off = pass ? 0 : kRaw * kABytes; off < 10 * kABytes; off += kABytes) {
          if (kh && pass == 2 && off == 8 * kABytes) {
            mbar_wait_sleep(sbase + kBarH, 0);
#pragma unroll 1
            for (uint32_t c = ti * 96 + 36; c < ti * 96 + 60; c++) load_acat(c);
          }
          mbar_wait_sleep(sbase + kBarEmptyA + 8 * ra.idx, ra.phase);
          const uint32_t fb = sbase + kBarFullA + 8 * ra.idx;
          mbar_expect_tx(fb, kABytes);
          bulk_load(sbase + kOffA + ra.idx * kABytes, xn + off, kABytes, fb);
          ra.next<kNA>();
        }
      }
      const uint32_t job = get_job();
      const uint32_t fti = (job & 7) * 2 + rank;
      mbar_wait_sleep(sbase + kBarO1, 0);
      uint32_t nend = 54;
#pragma unroll 1
      for (uint32_t n = 24 * kh + gh; n < nend; n++) {
        if (n == 40) mbar_wait_sleep(sbase + kBarO2, 0);
        load_acat(fti * 96 + final_chunk(n));
        if (rank == 0 && n < 54) {
          if (n >= 30)
            asm volatile("{\n.reg .b32 t;\n.reg .b64 v;\nmov.u32 t, %globaltimer_lo;\nmov.b64 v, {%1, t};\nst.relaxed.gpu.global.b64 [%0], v;\n}\n"
                         ::"l"(g_bal + kBalJob + job * 32 + 2 * kh), "r"((TAG << 8) | n) : "memory");
          if (n == kDecAt) mbar_arrive(sbase + kBarTrig);
        }
        if (n == 53) {
          mbar_wait_sleep(sbase + kBarDec, 0);
          nend = 54 + lds32(sbase + kOffDec);
        }
      }
      poll_ge_relaxed(reinterpret_cast<uint32_t*>(xnb + fti * kXnStride) + kFlagX + 32 * ((job >> 3) + 4 - 4 * kh), TAG * 4);
      mbar_arrive(sbase + kBarX);
    } else if (warp >= 10) {
      if (guest) {
        if (tid == 320) {
#pragma unroll 1
          for (int i = 0; i < 16; i++) {
            mbar_wait_sleep(sbase + kBarUnit, i & 1);
            red_release_add(reinterpret_cast<uint32_t*>(xnb + (((i & 7) * 2 + rank) * kXnStride + (kFlagGuest + (cl & 1) * 2 + (i >> 3)) * 4)));
          }
        }
        return;
      }
      if (warp == 10) {
        if (lane == 0) {
          mbar_wait(sbase + kBarUnit, 0);
          red_release_add(flags + kFlagLN);
          uint32_t par = 1;
#pragma unroll 1
          for (int u = 0; u < 5; u++) {
            mbar_wait_sleep(sbase + kBarUnit, par);
            par ^= 1;
            if (u == 3 && rank == 0) {
              const uint32_t idx = atomicInc(g_bal + kBalCnt + 32 * kh, 31);
              if (kh == 0) {
                st_relaxed(g_bal + kBalList + idx, (TAG << 8) | cl);
              } else {
                uint32_t v, tries = 0;
                const uint32_t tag = TAG & 0xFFFFFF;
                while (((v = ld_relaxed(g_bal + kBalList + 31 - idx)) >> 8) != tag && ++tries < 0x1000000) {}
                broadcast_word(sbase + kOffJob, v & 31, sbase + kBarJob);
              }
            }
            red_release_add(flags + kFlagUnit + (u == 4 ? 4 + kh : u));
            if (kh && u == 1) {
              mbar_wait_sleep(sbase + kBarUnit, par);
              par ^= 1;
              red_release_add(flags + kFlagD);
            }
          }
        }
      } else {
        if (lane == 0) {
          mbar_wait_sleep(sbase + kBarTag, 0);
          poll_ge_sleep(flags + kFlagUnit, TAG * 8);
          asm volatile("fence.proxy.async.global;" ::: "memory");
          mbar_arrive(sbase + kBarH);
          poll_ge_sleep(flags + kFlagD, TAG * 4);
          mbar_arrive(sbase + kBarHFree);
        }
        __syncwarp();
        const uint32_t job = get_job();
        if (lane == 0) {
          const uint32_t* ff = reinterpret_cast<const uint32_t*>(xnb + ((job & 7) * 2 + rank) * kXnStride);
          poll_ge_sleep(ff + kFlagUnit + 2 + kh, TAG * 8);
          asm volatile("fence.proxy.async.global;" ::: "memory");
          mbar_arrive(sbase + kBarO1);
          if (!kh) poll_ge_sleep(ff + kFlagUnit + 3, TAG * 8);
          poll_ge_sleep(ff + kFlagUnit + 4, TAG * 4);
          asm volatile("fence.proxy.async.global;" ::: "memory");
          mbar_arrive(sbase + kBarO2);
          poll_ge_sleep(ff + kFlagUnit + 5, TAG * 4);
          asm volatile("fence.proxy.async.global;" ::: "memory");
          mbar_arrive(sbase + kBarDec);
        }
        __syncwarp();
        const uint8_t* xp = reinterpret_cast<const uint8_t*>(x) + (uint32_t)(((((job & 7) * 2 + rank) * 128 + kh * 64 + lane) * kD + (job >> 3) * 160) * 2);
#pragma unroll
        for (int r = 0; r < 2; r++) {
          asm volatile("prefetch.global.L2 [%0];" ::"l"(xp + r * 32 * kD * 2));
          asm volatile("prefetch.global.L2 [%0];" ::"l"(xp + r * 32 * kD * 2 + 128));
          asm volatile("prefetch.global.L2 [%0];" ::"l"(xp + r * 32 * kD * 2 + 256));
        }
        if (lane == 0) {
          const uint32_t* ff = reinterpret_cast<const uint32_t*>(xnb + ((job & 7) * 2 + rank) * kXnStride);
          if (gh) {
            poll_ge_sleep(ff + kFlagGuest + (job >> 3), TAG);
            asm volatile("cp.async.bulk.prefetch.L2.global [%0], 20480;" ::"l"(reinterpret_cast<const uint8_t*>(g_xg) + (((job & 7) * 2 + rank) * 8 + (job >> 3) + 4 * kh) * 20480) : "memory");
          }
          mbar_arrive(sbase + kBarGuest);
        }
      }
      if (tid == 320 && rank == 0) {
        mbar_wait_sleep(sbase + kBarTrig, 0);
        uint32_t* bj = g_bal + kBalJob + get_job() * 32;
        const uint32_t tag = TAG & 0xFFFFFF;
        uint64_t pr, own;
        asm volatile("ld.relaxed.gpu.global.b64 %0, [%1];" : "=l"(pr) : "l"(bj + 2 - 2 * kh) : "memory");
        asm volatile("ld.relaxed.gpu.global.b64 %0, [%1];" : "=l"(own) : "l"(bj + 2 * kh) : "memory");
        uint32_t dec = ld_relaxed(bj + 8);
        if ((dec >> 8) != tag) {
          int dt = (int)((uint32_t)(own >> 32) - (uint32_t)(pr >> 32));
          dt = dt > 400 ? 400 : dt;
          const int lead = ((uint32_t)pr >> 8) == tag ? ((int)(own & 255) - (int)(pr & 255)) * 400 - dt + (kh ? 120 : -120) : 8000;
          int mine = 6 + ((lead * 82 + 32768) >> 16);
          mine = mine > 12 ? 12 : (mine < 0 ? 0 : mine);
          const uint32_t want = (tag << 8) | (kh ? 12 - mine : mine);
          const uint32_t old = atomicCAS(bj + 8, dec, want);
          dec = old == dec ? want : old;
        }
        broadcast_word(sbase + kOffDec, kh ? 12 - (dec & 255) : dec & 255, sbase + kBarDec);
      }
    }
  } else {
    const int w4 = warp & 3;
    const uint32_t t128 = tid & 127;
    Ring ra{0, 0}, rb{0, 0};
    uint32_t okA = 0, okB = 0;
    const uint32_t bar_self = 1 + wg, bar_other = 2 - wg;
#define TURN_WAIT() asm volatile("bar.sync %0, 256;" ::"r"(bar_self) : "memory")
#define TURN_PASS() asm volatile("bar.arrive %0, 256;" ::"r"(bar_other) : "memory")
#define TURN_WAIT_IF(c) asm volatile("{\n.reg .pred p;\nsetp.ne.u32 p, %1, 0;\n@p bar.sync %0, 256;\n}\n" ::"r"(bar_self), "r"((uint32_t)(c)) : "memory")
#define TURN_PASS_IF(c) asm volatile("{\n.reg .pred p;\nsetp.ne.u32 p, %1, 0;\n@p bar.arrive %0, 256;\n}\n" ::"r"(bar_other), "r"((uint32_t)(c)) : "memory")
#define PROBE_A() okA = mbar_probe(sbase + kBarFullA + 8 * ra.idx, ra.phase)
#define PROBE_B() okB = mbar_probe(sbase + kBarFullB + 8 * rb.idx, rb.phase)
#define TAKE_A(v) const uint32_t v = ra.idx; mbar_wait_unless(okA, sbase + kBarFullA + 8 * ra.idx, ra.phase); ra.next<kNA>()
#define TAKE_B(v, ok) const uint32_t v = rb.idx; mbar_wait_unless(ok, sbase + kBarFullB + 8 * rb.idx, rb.phase); rb.next<kNB>()
#define PROBE_BB() do { Ring r2_ = rb; r2_.next<kNB>(); okB = mbar_probe2(sbase + kBarFullB + 8 * rb.idx, rb.phase, sbase + kBarFullB + 8 * r2_.idx, r2_.phase); } while (0)
#define TAKE_BB(v, w) const uint32_t v = rb.idx, v##p = rb.phase; rb.next<kNB>(); const uint32_t w = rb.idx; \
  mbar_wait2_unless(okB, sbase + kBarFullB + 8 * v, v##p, sbase + kBarFullB + 8 * w, rb.phase); rb.next<kNB>()
#define PROBE_AB() okB = mbar_probe2(sbase + kBarFullA + 8 * ra.idx, ra.phase, sbase + kBarFullB + 8 * rb.idx, rb.phase)
#define TAKE_AB(v, w) const uint32_t v = ra.idx, w = rb.idx; \
  mbar_wait2_unless(okB, sbase + kBarFullA + 8 * v, ra.phase, sbase + kBarFullB + 8 * w, rb.phase); ra.next<kNA>(); rb.next<kNB>()
#define REL_A(s) mbar_arrive_if0(sbase + kBarEmptyA + 8 * (s), t128)
#define REL_B(s) mbar_arrive_cta_if0(sbase + kBarEmptyB + 8 * (s), (s) & 1, t128)

    const uint32_t descA0 = desc_lo(kSmemBase + kOffA, 1024) + wg * 512;
    constexpr uint32_t descBmn = desc_lo(kSmemBase + kOffB, 8192);
    constexpr uint32_t descBk = desc_lo(kSmemBase + kOffB, 16);
    constexpr uint32_t descBf = desc_lo(kSmemBase + kOffB, 4096);
    constexpr uint32_t hiA = desc_hi(128, 0), hiB = desc_hi(1024, 1), hiF = desc_hi(512, 2);

#define FINAL_ISSUE(ACC, sd0)                                                                  \
  TAKE_AB(sa, sb);                                                                              \
  const uint64_t da = mk(descA0 + sa * (kABytes >> 4), hiA);                                   \
  const uint64_t db = mk(descBf + sb * (kBBytes >> 4), hiF);                                   \
  TURN_WAIT();                                                                                 \
  WG_FENCE();                                                                                  \
  _Pragma("unroll") for (int s = 0; s < 4; s++) wgmma_ss_n160<1>(ACC, da + s * 128, db + s * 64, s ? 1 : (sd0)); \
  WG_COMMIT()
#define FINAL_NEXT(rel)                                                                        \
  TURN_PASS();                                                                                 \
  PROBE_AB();                                                                                   \
  if (rel) { WG_WAIT(1); REL_A(pa); REL_B(pb); }                                               \
  pa = sa; pb = sb

    if (guest) {
      asm volatile("barrier.cluster.wait.aligned;" ::: "memory");
      if (wg == 1) TURN_PASS();
      mbar_wait_sleep(sbase + kBarFullA, 0);
      okB = 0;
      uint32_t pk[40];
#pragma unroll
      for (int e = 0; e < 40; e++) pk[e] = 0;
#define GUEST_STORE(jb, n)                                                                     \
  do {                                                                                         \
    uint8_t* const gp = reinterpret_cast<uint8_t*>(g_xg) + (uint32_t)((((((jb) & 7) * 2 + rank) * 8 + wg * 4 + (cl & 1) * 2 + ((jb) >> 3)) * 1280 + t128) * 16); \
    *reinterpret_cast<uint4*>(gp + (n) * 4096) = make_uint4(pk[4 * (n)], pk[4 * (n) + 1], pk[4 * (n) + 2], pk[4 * (n) + 3]); \
    *reinterpret_cast<uint4*>(gp + (n) * 4096 + 2048) = make_uint4(pk[20 + 4 * (n)], pk[21 + 4 * (n)], pk[22 + 4 * (n)], pk[23 + 4 * (n)]); \
    if ((n) == 4) {                                                                            \
      __syncwarp();                                                                            \
      mbar_arrive_if0(sbase + kBarUnit, lane);                                                 \
    }                                                                                          \
  } while (0)
#pragma unroll 1
      for (int i = 0; i < 16; i++) {
        float acc[80];
        uint32_t pa = 0, pb = 0;
#pragma unroll
        for (int n = 0; n < kGuest; n++) {
          FINAL_ISSUE(acc, n != 0);
          FINAL_NEXT(n > 0);
          if (n < 5 && i > 0) GUEST_STORE(i - 1, n);
        }
        WG_WAIT(0);
        fence_regs(acc);
        REL_A(pa); REL_B(pb);
#pragma unroll
        for (int e = 0; e < 40; e++) pk[e] = pack_bf16(acc[2 * e], acc[2 * e + 1]);
      }
#pragma unroll
      for (int n = 0; n < 5; n++) GUEST_STORE(15, n);
      asm volatile("barrier.cluster.arrive.relaxed.aligned;" ::: "memory");
      asm volatile("barrier.cluster.wait.aligned;" ::: "memory");
      return;
    }
    uint32_t nmb, nrh, nrl;
#define NORM_RAW(c0, c1)                                                                       \
  do {                                                                                         \
    _Pragma("unroll 1") for (int c = (c0); c < (c1); c++) {                                    \
      const uint32_t rdst = sbase + kOffA + c * kABytes + tid * 64;                            \
      uint32_t v[16];                                                                          \
      _Pragma("unroll") for (int i = 0; i < 4; i++)                                            \
        asm volatile("ld.shared.v4.u32 {%0, %1, %2, %3}, [%4];" : "=r"(v[4 * i]), "=r"(v[4 * i + 1]), "=r"(v[4 * i + 2]), "=r"(v[4 * i + 3]) : "r"(rdst + ((i + (tid >> 1)) & 3) * 16) : "memory"); \
      _Pragma("unroll") for (int e = 0; e < 16; e++) {                                         \
        const uint32_t cc = hsub2(v[e], nmb);                                                  \
        v[e] = hfma2(cc, nrh, hmul2(cc, nrl));                                                 \
      }                                                                                        \
      _Pragma("unroll") for (int i = 0; i < 4; i++)                                            \
        asm volatile("st.shared.v4.u32 [%0], {%1, %2, %3, %4};" ::"r"(rdst + ((i + (tid >> 1)) & 3) * 16), "r"(v[4 * i]), "r"(v[4 * i + 1]), "r"(v[4 * i + 2]), "r"(v[4 * i + 3]) : "memory"); \
    }                                                                                          \
    asm volatile("fence.proxy.async.shared::cta;" ::: "memory");                               \
    asm volatile("bar.sync %0, 128;" ::"r"(5 + wg) : "memory");                                \
  } while (0)
    {
      const int lr = 16 * j + (tid >> 4);
      uint32_t y[20];
      uint8_t* const dst = reinterpret_cast<uint8_t*>(flags) + (uint32_t)(4096 + lr * 128 + ((lane >> 3) & 1) * kABytes + ((lane ^ lr) & 7) * 16);
      const uint32_t tagw = tag + 1;
      uint32_t (&w)[20] = xin;
      {
        float s4[4] = {0.f, 0.f, 0.f, 0.f};
#pragma unroll
        for (int e = 0; e < 20; e++) s4[e & 3] += bf_lo(w[e]) + bf_hi(w[e]);
        float s = (s4[0] + s4[1]) + (s4[2] + s4[3]);
#pragma unroll
        for (int o = 1; o < 16; o <<= 1) s += __shfl_xor_sync(0xffffffffu, s, o);
        const float mean = s * (1.f / kD);
        float q4[4] = {0.f, 0.f, 0.f, 0.f};
#pragma unroll
        for (int e = 0; e < 20; e++) {
          const float d0 = bf_lo(w[e]) - mean, d1 = bf_hi(w[e]) - mean;
          q4[(2 * e) & 3] = fmaf(d0, d0, q4[(2 * e) & 3]); q4[(2 * e + 1) & 3] = fmaf(d1, d1, q4[(2 * e + 1) & 3]);
        }
        float q = (q4[0] + q4[1]) + (q4[2] + q4[3]);
#pragma unroll
        for (int o = 1; o < 16; o <<= 1) q += __shfl_xor_sync(0xffffffffu, q, o);
        const uint32_t mb = pack_bf16(mean, mean);
        float sd;
        asm("sqrt.approx.ftz.f32 %0, %1;" : "=f"(sd) : "f"(bf_lo(pack_bf16(bf_lo(pack_bf16(q * (1.f / kD), 0.f)) + 1e-5f, 0.f))));
        const uint32_t md = pack_bf16(mean, sd);
        asm volatile("st.shared.u32 [%0], %1;" ::"r"(sbase + kOffStat + (tid >> 4) * 4), "r"(md) : "memory");
        asm volatile("bar.sync 7, 256;" ::: "memory");
        asm volatile("{\n.reg .pred p;\n.reg .b64 v;\n.reg .b32 m;\nsetp.ne.u32 p, %3, 0;\nld.shared.u32 m, [%2];\nmov.b64 v, {%1, m};\n@p st.relaxed.gpu.global.b64 [%0], v;\n}\n"
                     ::"l"(stat + (16 * j + (tid & 15)) * 8), "r"(tagw), "r"(sbase + kOffStat + (tid & 15) * 4), "r"((uint32_t)(tid < 16)) : "memory");
        const float rinv = rcp(bf_hi(md));
        const uint32_t rh = pack_bf16(rinv, rinv);
        const float rlo = rinv - bf_lo(rh);
        const uint32_t rl = pack_bf16(rlo, rlo);
#pragma unroll
        for (int e = 0; e < 20; e++) {
          const uint32_t c = hsub2(w[e], mb);
          y[e] = hfma2(c, rh, hmul2(c, rl));
        }
      }
      const uint32_t rrow = tid >> 1;
      uint32_t md;
      asm volatile("{\n.reg .pred p;\n.reg .u32 c, t;\n.reg .b64 v;\nmov.u32 c, 0;\n"
                   "LAB_POLL:\nld.relaxed.gpu.global.b64 v, [%1];\nmov.b64 {t, %0}, v;\nsetp.eq.u32 p, t, %2;\n"
                   "vote.sync.all.pred p, p, 0xffffffff;\n@p bra.uni DONE;\n"
                   "add.u32 c, c, 1;\nsetp.lt.u32 p, c, 0x1000000;\n@p bra.uni LAB_POLL;\ntrap;\nDONE:\n}\n"
                   : "=&r"(md) : "l"(stat + rrow * 8), "r"(tagw) : "memory");
      asm volatile("barrier.cluster.wait.aligned;" ::: "memory");
      asm volatile("st.shared.u32 [%0], %1;" ::"r"(sbase + kOffTag), "r"(tagw) : "memory");
      mbar_arrive_if0(sbase + kBarTag, tid);
#pragma unroll
      for (int t = 0; t < 5; t++)
        *reinterpret_cast<uint4*>(dst + t * 2 * kABytes) = make_uint4(y[4 * t], y[4 * t + 1], y[4 * t + 2], y[4 * t + 3]);
      __syncwarp();
      mbar_arrive_if0(sbase + kBarUnit, lane);
      asm volatile("setmaxnreg.inc.sync.aligned.u32 240;");
      mbar_wait_unless(0, sbase + kBarFullA, 0);
      nmb = __byte_perm(md, md, 0x1010);
      const float rinv = rcp(bf_hi(md));
      nrh = pack_bf16(rinv, rinv);
      const float rlo = rinv - bf_lo(nrh);
      nrl = pack_bf16(rlo, rlo);
    }

    if (wg == 1) TURN_PASS();
    float o[96];
    float dr0, dr1;
    uint64_t pend = __cvta_generic_to_global(g_acat) + (uint32_t)((ti * 96 + 36 + 3 * j) * kABytes + wg * 8192 + w4 * 256 + lane * 4);

#define DRAIN_PART(part, cnt)                                                                 \
  do {                                                                                        \
    asm volatile("" : "+f"(dr0), "+f"(dr1)::"memory");                                        \
    _Pragma("unroll") for (int n8 = (cnt) * (part); n8 < (cnt) * (part) + (cnt); n8++) {      \
      stg32(pend + (n8 >> 3) * kABytes + (n8 & 7) * 1024, pack_bf16(o[4 * n8] * dr0, o[4 * n8 + 1] * dr0)); \
      stg32(pend + (n8 >> 3) * kABytes + (n8 & 7) * 1024 + 128, pack_bf16(o[4 * n8 + 2] * dr1, o[4 * n8 + 3] * dr1)); \
    }                                                                                         \
    if ((cnt) * (part) + (cnt) == 24) {                                                       \
      __syncwarp();                                                                           \
      mbar_arrive_if0(sbase + kBarUnit, lane);                                                \
    }                                                                                         \
  } while (0)

    float qa[96];
    {
      float (&g)[96] = qa;
      uint32_t pa = 0, pb0 = 0, pb1 = 0;
#pragma unroll 1
      for (int kc = 0; kc < 10; kc++) {
        if (kc < kRaw) NORM_RAW(kc, kc + 1);
        WG_WAIT(0);
        if (kc > 0) { REL_A(pa); REL_B(pb0); REL_B(pb1); }
        okA = 0; okB = 0;
        TAKE_A(sa);
        TAKE_BB(sb0, sb1);
        const uint64_t da = mk(descA0 + sa * (kABytes >> 4), hiB);
        const uint64_t db0 = mk(descBmn + sb0 * (kBBytes >> 4), hiB), db1 = mk(descBmn + sb1 * (kBBytes >> 4), hiB);
        TURN_WAIT();
        WG_FENCE();
#pragma unroll
        for (int s = 0; s < 4; s++) {
          wgmma_ss_n192<1>(g, da + s * 2, db0 + s * 128, (kc | s) != 0);
          wgmma_ss_n192<1>(o, da + s * 2, db1 + s * 128, (kc | s) != 0);
        }
        WG_COMMIT();
        TURN_PASS();
        pa = sa; pb0 = sb0; pb1 = sb1;
      }
      PROBE_AB();
      WG_WAIT(0);
      fence_regs(g); fence_regs(o);
      REL_A(pa); REL_B(pb0); REL_B(pb1);
#pragma unroll
      for (int e = 0; e < 96; e++) o[e] *= g[e];
      fence_regs(o);
      dr0 = 1.f; dr1 = 1.f;
    }

    const float cs = 0.07216878364870322f * 1.4426950408889634f;
    uint32_t pl[16];
    float l0, l1;
    uint32_t pa, pb;
#define LAST_PV(sv)                                                                            \
  do {                                                                                         \
    const uint64_t dv = mk(descBmn + (sv) * (kBBytes >> 4), hiB);                              \
    _Pragma("unroll") for (int s = 0; s < 4; s++)                                              \
      wgmma_rs_n192<1>(o, pl[4 * s], pl[4 * s + 1], pl[4 * s + 2], pl[4 * s + 3], dv + s * 128, 1); \
    WG_COMMIT();                                                                               \
  } while (0)
#define LAST_PV_DONE(sv)                                                                       \
  do {                                                                                         \
    l0 += __shfl_xor_sync(0xffffffffu, l0, 1); l1 += __shfl_xor_sync(0xffffffffu, l1, 1);      \
    l0 += __shfl_xor_sync(0xffffffffu, l0, 2); l1 += __shfl_xor_sync(0xffffffffu, l1, 2);      \
    dr0 = rcp(l0); dr1 = rcp(l1);                                                              \
    WG_WAIT(1);                                                                                \
    fence_regs(o);                                                                             \
    REL_B(sv);                                                                                 \
  } while (0)
#define Q_FIRST()                                                                              \
  _Pragma("unroll") for (int s = 0; s < 4; s++)                                                \
    wgmma_ss_n192<1>(qa, mk(descA0 + sa * (kABytes >> 4), hiB) + s * 2, mk(descBmn + sb * (kBBytes >> 4), hiB) + s * 128, s != 0); \
  WG_COMMIT();                                                                                 \
  TURN_PASS();                                                                                 \
  PROBE_AB();                                                                                   \
  pa = sa; pb = sb
    {
      TAKE_AB(sa, sb);
      TURN_WAIT();
      WG_FENCE();
      Q_FIRST();
    }
#pragma unroll 1
    for (int t = 0;; t++) {
      uint32_t frag[48];
      float sc[32];
      uint32_t p[16];
      float mc0, mc1;
      float s0, s1;
#define QK(DST, DESC)                                                                          \
  _Pragma("unroll") for (int ks = 0; ks < 12; ks++)                                            \
    wgmma_rs_n64<0>(DST, frag[4 * ks], frag[4 * ks + 1], frag[4 * ks + 2], frag[4 * ks + 3], (DESC) + (ks >> 2) * 512 + (ks & 3) * 2, ks != 0);
#define SCALE_SC()                                                                             \
  _Pragma("unroll") for (int n8 = 0; n8 < 8; n8++) {                                           \
    sc[4 * n8] = fmaf(sc[4 * n8], cs, -mc0); sc[4 * n8 + 1] = fmaf(sc[4 * n8 + 1], cs, -mc0);  \
    sc[4 * n8 + 2] = fmaf(sc[4 * n8 + 2], cs, -mc1); sc[4 * n8 + 3] = fmaf(sc[4 * n8 + 3], cs, -mc1); \
  }
#define EXP_SC()                                                                               \
  _Pragma("unroll") for (int n8 = 0; n8 < 8; n8++) {                                           \
    const float e0 = ex2(sc[4 * n8]), e1 = ex2(sc[4 * n8 + 1]), e2 = ex2(sc[4 * n8 + 2]), e3 = ex2(sc[4 * n8 + 3]); \
    if (n8 == 0) { s0 = e0 + e1; s1 = e2 + e3; } else { s0 += e0 + e1; s1 += e2 + e3; }        \
    p[2 * n8] = pack_bf16(e0, e1); p[2 * n8 + 1] = pack_bf16(e2, e3);                          \
  }
      {
        DRAIN_PART(0, 3);
#pragma unroll
        for (int kc = 1; kc < 10; kc++) {
          if (kc == 8 && kh && t == 1) {
#pragma unroll 1
            for (int n = 100; n < 124; n++) {
              FINAL_ISSUE(o, n != 100);
              FINAL_NEXT(true);
            }
          }
          TAKE_AB(sa, sb);
          const uint64_t da = mk(descA0 + sa * (kABytes >> 4), hiB);
          const uint64_t db = mk(descBmn + sb * (kBBytes >> 4), hiB);
          if (kc < 9) TURN_WAIT(); else TURN_WAIT_IF(wg);
          WG_FENCE();
#pragma unroll
          for (int s = 0; s < 4; s++) { wgmma_ss_n192<1>(qa, da + s * 2, db + s * 128, (kc | s) != 0); }
          WG_COMMIT();
          if (kc < 8) TURN_PASS(); else TURN_PASS_IF(kc == 8 ? wg : wg ^ 1);
          if (kc < 9) PROBE_AB(); else PROBE_B();
          if (kc > 0) { WG_WAIT(1); REL_A(pa); REL_B(pb); }
          if (kc < 8) DRAIN_PART(kc, 3);
          if (kc == 7) {
            pend += (int64_t)(t == 0 ? -36 * kABytes : 24 * kABytes);
            asm volatile("" : "+l"(pend));
          }
          if (kc >= 8 && kh && t == 1) {
            uint8_t* const dp = reinterpret_cast<uint8_t*>(g_xd) + (uint32_t)(((ti * 8 + wg * 4 + nq) * 1280 + (kc - 8) * 128 + t128) * 16);
#pragma unroll
            for (int q = 0; q < 5; q++) {
              const int e = (kc - 8) * 40 + 8 * q;
#pragma unroll
              for (int i = e; i < e + 8; i++) asm volatile("" : "+f"(o[i])::"memory");
              *reinterpret_cast<uint4*>(dp + q * 4096) = make_uint4(pack_bf16(o[e], o[e + 1]), pack_bf16(o[e + 2], o[e + 3]),
                                                                   pack_bf16(o[e + 4], o[e + 5]), pack_bf16(o[e + 6], o[e + 7]));
            }
            if (kc == 9) {
              __syncwarp();
              mbar_arrive_if0(sbase + kBarUnit, lane);
            }
          }
          pa = sa; pb = sb;
        }
        TAKE_B(sk, okB);
        const uint64_t dk = mk(descBk + sk * (kBBytes >> 4), hiB);
        WG_WAIT(0);
        fence_regs(qa);
#pragma unroll
        for (int e = 0; e < 48; e++) frag[e] = pack_bf16(qa[2 * e], qa[2 * e + 1]);
        TURN_WAIT_IF(wg ^ 1);
        WG_FENCE();
        QK(sc, dk);
        WG_COMMIT();
        TURN_PASS();
        PROBE_BB();
        REL_A(pa); REL_B(pb);
        WG_WAIT(0);
        fence_regs(sc);
        REL_B(sk);
      }
      {
        float m0 = fmaxf(fmaxf(sc[0], sc[1]), fmaxf(sc[4], sc[5])), m1 = fmaxf(fmaxf(sc[2], sc[3]), fmaxf(sc[6], sc[7]));
        m0 = fmaxf(m0, __shfl_xor_sync(0xffffffffu, m0, 1)); m1 = fmaxf(m1, __shfl_xor_sync(0xffffffffu, m1, 1));
        m0 = fmaxf(m0, __shfl_xor_sync(0xffffffffu, m0, 2)); m1 = fmaxf(m1, __shfl_xor_sync(0xffffffffu, m1, 2));
        mc0 = m0 * cs; mc1 = m1 * cs;
        l0 = 0.f; l1 = 0.f;
        SCALE_SC();
        EXP_SC();
      }
      int b = 0;
#pragma unroll 1
      while (true) {
        if (__builtin_expect(__any_sync(0xffffffffu, !(s0 + s1 <= 1048576.f)), 0)) {
          float x0 = fmaxf(sc[0], sc[1]), x1 = fmaxf(sc[2], sc[3]);
#pragma unroll
          for (int n8 = 1; n8 < 8; n8++) {
            x0 = fmaxf(x0, fmaxf(sc[4 * n8], sc[4 * n8 + 1]));
            x1 = fmaxf(x1, fmaxf(sc[4 * n8 + 2], sc[4 * n8 + 3]));
          }
          x0 = fmaxf(x0, __shfl_xor_sync(0xffffffffu, x0, 1)); x1 = fmaxf(x1, __shfl_xor_sync(0xffffffffu, x1, 1));
          x0 = fmaxf(x0, __shfl_xor_sync(0xffffffffu, x0, 2)); x1 = fmaxf(x1, __shfl_xor_sync(0xffffffffu, x1, 2));
          x0 = fmaxf(x0, 0.f); x1 = fmaxf(x1, 0.f);
          const float a0 = ex2(-x0), a1 = ex2(-x1);
          mc0 += x0; mc1 += x1;
          l0 *= a0; l1 *= a1;
          s0 = 0.f; s1 = 0.f;
#pragma unroll
          for (int n8 = 0; n8 < 8; n8++) {
            const float e0 = ex2(sc[4 * n8] - x0), e1 = ex2(sc[4 * n8 + 1] - x0), e2 = ex2(sc[4 * n8 + 2] - x1), e3 = ex2(sc[4 * n8 + 3] - x1);
            s0 += e0 + e1; s1 += e2 + e3;
            p[2 * n8] = pack_bf16(e0, e1); p[2 * n8 + 1] = pack_bf16(e2, e3);
          }
#pragma unroll
          for (int n8 = 0; n8 < 24; n8++) {
            o[4 * n8] *= a0; o[4 * n8 + 1] *= a0; o[4 * n8 + 2] *= a1; o[4 * n8 + 3] *= a1;
          }
        }
        l0 += s0; l1 += s1;
        if (b == 7) break;
        TAKE_BB(sk, sv);
        const uint64_t dk = mk(descBk + sk * (kBBytes >> 4), hiB);
        const uint64_t dv = mk(descBmn + sv * (kBBytes >> 4), hiB);
        TURN_WAIT();
        WG_FENCE();
        QK(sc, dk);
        WG_COMMIT();
#pragma unroll
        for (int s = 0; s < 4; s++)
          wgmma_rs_n192<1>(o, p[4 * s], p[4 * s + 1], p[4 * s + 2], p[4 * s + 3], dv + s * 128, (b | s) != 0);
        WG_COMMIT();
        TURN_PASS();
        PROBE_BB();
        WG_WAIT(1);
        fence_regs(sc);
        REL_B(sk);
        SCALE_SC();
        fence_regs(sc);
        WG_WAIT(0);
        fence_regs(o); fence_regs(p);
        REL_B(sv);
        EXP_SC();
        b++;
      }
      PROBE_A();
#pragma unroll
      for (int e = 0; e < 16; e++) pl[e] = p[e] ^ blockIdx.y;
      if (t == 3) break;
      {
        TAKE_BB(sv, sb); TAKE_A(sa);
        TURN_WAIT();
        WG_FENCE();
        LAST_PV(sv);
        Q_FIRST();
        LAST_PV_DONE(sv);
      }
    }

    {
      float acc[80];
      const int half = wg ^ kh;
      uint32_t gd[20];
      {
        TAKE_BB(sv, sb); TAKE_A(sa);
        const uint64_t da = mk(descA0 + sa * (kABytes >> 4), hiA), db = mk(descBf + sb * (kBBytes >> 4), hiF);
        TURN_WAIT();
        WG_FENCE();
        LAST_PV(sv);
#pragma unroll
        for (int s = 0; s < 4; s++) wgmma_ss_n160<1>(acc, da + s * 128, db + s * 64, s != 0);
        WG_COMMIT();
        FINAL_NEXT(false);
        LAST_PV_DONE(sv);
        DRAIN_PART(0, 3);
      }
#pragma unroll
      for (int n = 1; n < 8; n++) {
        FINAL_ISSUE(acc, 1);
        FINAL_NEXT(true);
        DRAIN_PART(n, 3);
        if (n == 4) {
          const uint32_t job = kh ? lds32(sbase + kOffJob) : (cl & 31);
          const uint8_t* dp = reinterpret_cast<const uint8_t*>(g_xd) + (uint32_t)(((((job & 7) * 2 + rank) * 8 + (job >> 3) + 4 * kh) * 1280 + half * 128 + t128) * 16);
#pragma unroll
          for (int i = 0; i < 5; i++)
            asm volatile("ld.global.cg.v4.u32 {%0, %1, %2, %3}, [%4];" : "=r"(gd[4 * i]), "=r"(gd[4 * i + 1]), "=r"(gd[4 * i + 2]), "=r"(gd[4 * i + 3]) : "l"(dp + i * 4096) : "memory");
        }
      }
#pragma unroll 1
      for (int n = 8; n < 18; n++) {
        FINAL_ISSUE(acc, 1);
        FINAL_NEXT(true);
        const uint32_t t0 = pack_bf16(silu(bf_lo(gd[0])), silu(bf_hi(gd[0]))), t1 = pack_bf16(silu(bf_lo(gd[1])), silu(bf_hi(gd[1])));
#pragma unroll
        for (int e = 0; e < 18; e++) gd[e] = gd[e + 2];
        gd[18] = t0; gd[19] = t1;
      }
      int lim = 50;
#pragma unroll 1
      for (int n = 18 + 24 * kh + gh; n < lim; n++) {
        FINAL_ISSUE(acc, 1);
        FINAL_NEXT(true);
        if (n == 49) {
          mbar_wait_unless(0, sbase + kBarDec, 0);
          lim = 50 + __shfl_sync(0xffffffffu, lds32(sbase + kOffDec), 0);
        }
      }
      const uint32_t job = kh ? lds32(sbase + kOffJob) : (cl & 31);
      const uint32_t fti = (job & 7) * 2 + rank, fnq = job >> 3, fj = fnq + 4 * kh;
      if ((kh | wg) == 0) { TURN_WAIT(); TURN_PASS(); }
      if (!half && gh) {
        mbar_wait_unless(0, sbase + kBarGuest, 0);
        const uint8_t* gp = reinterpret_cast<const uint8_t*>(g_xg) + (uint32_t)(((fti * 8 + fj) * 1280 + t128) * 16);
        uint32_t gs[40];
#pragma unroll
        for (int i = 0; i < 10; i++)
          asm volatile("ld.global.cg.v4.u32 {%0, %1, %2, %3}, [%4];" : "=r"(gs[4 * i]), "=r"(gs[4 * i + 1]), "=r"(gs[4 * i + 2]), "=r"(gs[4 * i + 3])
                       : "l"(gp + (i % 5) * 4096 + (i / 5) * 2048) : "memory");
        WG_WAIT(0);
        fence_regs(acc);
#pragma unroll
        for (int e = 0; e < 40; e++) { acc[2 * e] += bf_lo(gs[e]); acc[2 * e + 1] += bf_hi(gs[e]); }
      }
      TURN_WAIT();
#pragma unroll 1
      for (int i = 0; i < 4; i++) {
        if (half) {
          mbar_wait_unless(0, sbase + kBarFullA + 8 * ra.idx, ra.phase);
          mbar_wait_unless(0, sbase + kBarFullB + 8 * rb.idx, rb.phase);
        }
        const uint64_t da = mk(descA0 + ra.idx * (kABytes >> 4), hiA), db = mk(descBf + rb.idx * (kBBytes >> 4), hiF);
        ra.next<kNA>(); rb.next<kNB>();
        WG_FENCE();
#pragma unroll
        for (int s = 0; s < 4; s++) wgmma_ss_n160<1>(acc, da + s * 128, db + s * 64, 1);
        WG_COMMIT();
      }
      TURN_PASS();
      mbar_arrive_if0(sbase + kBarDone, t128);
      asm volatile("barrier.cluster.arrive.relaxed.aligned;" ::: "memory");
      const uint32_t hand = sbase + kOffB + rb.idx * kBBytes + t128 * 16;
      rb.next<kNB>();
      const uint8_t* const xr = reinterpret_cast<const uint8_t*>(g_xs) + (uint32_t)(((fti * 8 + (fj ^ 4)) * 1536 + half * 768 + t128) * 16);
      uint32_t xtag;
      asm volatile("ld.shared.u32 %0, [%1];" : "=r"(xtag) : "r"(sbase + kOffTag) : "memory");
      xtag = ((xtag & 0x3FFF) + 0x80) << 16;
      const uint32_t blk = (uint32_t)((fti * 128 + kh * 64 + w4 * 16) * kD + fnq * 160 + half * 80) * 2;
      const uint32_t stg = sbase + kOffB + rb.idx * kBBytes + warp * (16 * 160);
      uint32_t goff[5], xv[20];
#pragma unroll
      for (int i = 0; i < 5; i++) {
        const uint32_t pc = lane + 32 * i, row = (pc * 205) >> 11, c = pc - row * 10;
        goff[i] = blk + row * (kD * 2) + c * 16;
        asm volatile("ld.global.nc.v4.u32 {%0, %1, %2, %3}, [%4];" : "=r"(xv[4 * i]), "=r"(xv[4 * i + 1]), "=r"(xv[4 * i + 2]), "=r"(xv[4 * i + 3])
                     : "l"(reinterpret_cast<const uint8_t*>(x) + goff[i]) : "memory");
      }
      WG_WAIT(0);
      fence_regs(acc);
      if (half) {
        uint8_t* const xs = reinterpret_cast<uint8_t*>(g_xs) + (uint32_t)(((fti * 8 + fj) * 1536 + t128) * 16);
#pragma unroll
        for (int q = 0; q < 12; q++) {
          if (q == 11)
            asm volatile("{\n.reg .pred p;\nsetp.eq.u32 p, %1, 0;\n@p red.relaxed.gpu.global.add.u32 [%0], 1;\n}\n" ::"l"(xnb + (fti * kXnStride + (kFlagX + 32 * fj) * 4)), "r"(lane) : "memory");
          const int e = (q / 6) * 40 + (q % 6) * 7;
          const bool last = (q % 6) == 5;
          asm volatile("st.relaxed.gpu.global.v4.u32 [%0], {%1, %2, %3, %4};"
                       ::"l"(xs + q * 2048), "r"(pack_bf16(acc[e], acc[e + 1])), "r"(pack_bf16(acc[e + 2], acc[e + 3])),
                       "r"(pack_bf16(acc[e + 4], last ? 0.f : acc[(e + 5) % 80])), "r"(last ? xtag : pack_bf16(acc[(e + 6) % 80], __uint_as_float(xtag))) : "memory");
        }
      } else {
#pragma unroll
        for (int q = 0; q < 10; q++)
          asm volatile("st.shared.v4.f32 [%0], {%1, %2, %3, %4};" ::"r"(hand + q * 2048), "f"(acc[40 + 4 * q]), "f"(acc[41 + 4 * q]), "f"(acc[42 + 4 * q]), "f"(acc[43 + 4 * q]) : "memory");
        asm volatile("bar.arrive 3, 256;" ::: "memory");
      }
      const uint32_t sm = stg + (lane & 15) * 160 + (lane >> 4) * 16;
      uint32_t r[24];
      mbar_wait_unless(0, sbase + kBarX, 0);
      uint32_t bad, tries = 0;
      do {
#pragma unroll
        for (int q = 0; q < 6; q++)
          asm volatile("ld.relaxed.gpu.global.v4.u32 {%0, %1, %2, %3}, [%4];"
                       : "=r"(r[4 * q]), "=r"(r[4 * q + 1]), "=r"(r[4 * q + 2]), "=r"(r[4 * q + 3]) : "l"(xr + q * 2048) : "memory");
        bad = 0;
#pragma unroll
        for (int q = 0; q < 6; q++) bad |= r[4 * q + 3] ^ xtag;
      } while (__any_sync(0xffffffffu, bad > 0xFFFFu) && ++tries < 0x400000);
      if (half) {
        asm volatile("bar.sync 3, 256;" ::: "memory");
#pragma unroll
        for (int q = 0; q < 10; q++)
          asm volatile("ld.shared.v4.f32 {%0, %1, %2, %3}, [%4];" : "=f"(acc[4 * q]), "=f"(acc[4 * q + 1]), "=f"(acc[4 * q + 2]), "=f"(acc[4 * q + 3]) : "r"(hand + q * 2048) : "memory");
      }
#pragma unroll
      for (int q = 0; q < 5; q++) {
        uint32_t m[4];
#pragma unroll
        for (int e = 0; e < 4; e++) {
          const int v0 = 8 * q + 2 * e, v1 = v0 + 1;
          const uint32_t w0 = r[(v0 / 7) * 4 + (v0 % 7) / 2], w1 = r[(v1 / 7) * 4 + (v1 % 7) / 2];
          const float r0 = ((v0 % 7) & 1 ? bf_hi(w0) : bf_lo(w0));
          const float r1 = ((v1 % 7) & 1 ? bf_hi(w1) : bf_lo(w1));
          m[e] = hmul2(pack_bf16(acc[8 * q + 2 * e] + r0, acc[8 * q + 2 * e + 1] + r1), gd[4 * q + e]);
        }
        asm volatile("stmatrix.sync.aligned.m8n8.x4.shared.b16 [%0], {%1, %2, %3, %4};" ::"r"(sm + q * 32), "r"(m[0]), "r"(m[1]), "r"(m[2]), "r"(m[3]) : "memory");
      }
      __syncwarp();
#pragma unroll
      for (int i = 0; i < 5; i++) {
        uint32_t m0, m1, m2, m3;
        asm volatile("ld.shared.v4.u32 {%0, %1, %2, %3}, [%4];" : "=r"(m0), "=r"(m1), "=r"(m2), "=r"(m3) : "r"(stg + lane * 16 + i * 512) : "memory");
        *reinterpret_cast<uint4*>(reinterpret_cast<uint8_t*>(out) + goff[i]) =
            make_uint4(hadd2(xv[4 * i], m0), hadd2(xv[4 * i + 1], m1), hadd2(xv[4 * i + 2], m2), hadd2(xv[4 * i + 3], m3));
      }
      asm volatile("barrier.cluster.wait.aligned;" ::: "memory");
    }
  }
}

typedef CUresult (*EncodeFn)(CUtensorMap*, CUtensorMapDataType, cuuint32_t, void*, const cuuint64_t*, const cuuint64_t*,
                             const cuuint32_t*, const cuuint32_t*, CUtensorMapInterleave, CUtensorMapSwizzle,
                             CUtensorMapL2promotion, CUtensorMapFloatOOBfill);

void make_map(EncodeFn enc, CUtensorMap* tm, const void* base, uint64_t rows, uint64_t cols, uint32_t cw, uint32_t nch,
              uint32_t brows = 64) {
  cuuint64_t dims[3] = {cw, rows, cols / cw};
  cuuint64_t strides[2] = {cols * 2, cw * 2};
  cuuint32_t box[3] = {cw, brows, nch};
  cuuint32_t es[3] = {1, 1, 1};
  enc(tm, CU_TENSOR_MAP_DATA_TYPE_BFLOAT16, 3, const_cast<void*>(base), dims, strides, box, es, CU_TENSOR_MAP_INTERLEAVE_NONE,
      cw == 64 ? CU_TENSOR_MAP_SWIZZLE_128B : CU_TENSOR_MAP_SWIZZLE_64B, CU_TENSOR_MAP_L2_PROMOTION_L2_128B,
      CU_TENSOR_MAP_FLOAT_OOB_FILL_NONE);
}

}

extern "C" void kernel_launch(void* const* d_in, const int* in_sizes, int n_in, void* d_out, int out_size) {
  (void)in_sizes; (void)n_in; (void)out_size;
  static EncodeFn enc = nullptr;
  static uint8_t* xnb = nullptr;
  static int grid = 128;
  if (!enc) {
    void* fn = nullptr;
    cudaDriverEntryPointQueryResult qr;
    cudaGetDriverEntryPoint("cuTensorMapEncodeTiled", &fn, cudaEnableDefault, &qr);
    enc = (EncodeFn)fn;
    cudaGetSymbolAddress((void**)&xnb, g_xn);
    cudaFuncSetAttribute(fused_kernel, cudaFuncAttributeMaxDynamicSharedMemorySize, kSmemBytes);
    cudaLaunchConfig_t cfg = {};
    cfg.gridDim = dim3(132);
    cfg.blockDim = dim3(384);
    cfg.dynamicSmemBytes = kSmemBytes;
    int nc = 0;
    if (cudaOccupancyMaxActiveClusters(&nc, fused_kernel, &cfg) == cudaSuccess && nc >= 66) grid = 132;
    (void)cudaGetLastError();
  }
  CUtensorMap tmWq, tmK, tmV, tmWg, tmWu, tmWo, tmWd, tmX;
  make_map(enc, &tmX, d_in[0], 2048, 640, 64, kRaw, 128);
  make_map(enc, &tmK, d_in[1], 32 * 2048, 192, 64, 3);
  make_map(enc, &tmV, d_in[2], 32 * 2048, 192, 64, 3);
  make_map(enc, &tmWq, d_in[3], 640, 6144, 64, 3);
  make_map(enc, &tmWo, d_in[4], 6144, 640, 32, 5);
  make_map(enc, &tmWg, d_in[6], 640, 1536, 64, 3);
  make_map(enc, &tmWu, d_in[7], 640, 1536, 64, 3);
  make_map(enc, &tmWd, d_in[8], 1536, 640, 32, 5);
  fused_kernel<<<grid, 384, kSmemBytes>>>((const __nv_bfloat16*)d_in[0], (__nv_bfloat16*)d_out, xnb, tmX, tmWg, tmWu, tmWq, tmK,
                                         tmV, tmWo, tmWd);
}
```
